```python
import torch

def _softmax(x, axis=-1):
    return torch.softmax(x, dim=axis)
def _gelu(x):
    return torch.nn.functional.gelu(x, approximate="tanh")
def _silu(x):
    return torch.nn.functional.silu(x)
def _sigmoid(x):
    return torch.sigmoid(x)
def _layernorm(x, axis=-1, eps=1e-5):
    m = x.mean(dim=axis, keepdim=True)
    v = x.var(dim=axis, keepdim=True, unbiased=False)
    return (x - m) / torch.sqrt(v + eps)
def _scatter_add(tgt, idx, src, axis=0):
    return tgt.clone().index_add_(axis, idx, src)
def _segment_sum(src, seg, n):
    out = torch.zeros((n,) + src.shape[1:], dtype=src.dtype)
    return out.index_add_(0, seg, src)
def _pad(x, pw):
    flat = tuple(v for pair in reversed(pw) for v in pair)
    return torch.nn.functional.pad(x, flat)

kernel_name = 'concat_heads__gqa_block_cached__gqa_block_cached__decode'

def setup_inputs():

    _w = (lambda a: (lambda t: t.to(torch.bfloat16) if t.is_floating_point() else t)(torch.as_tensor(a)))
    def _A_setup():
        B, Sq, D = 2, 1, 448
        Hq, Hkv, Sk, Dh = 16, 8, 4096, 256
        assert Hq % Hkv == 0, (Hq, Hkv)
        return {
            "x": _w((lambda *s: torch.randn(*s, dtype=torch.bfloat16) * 0.8)(B, Sq, D)),
            "k_cache": _w((lambda *s: torch.randn(*s, dtype=torch.bfloat16) * 0.8)(B, Hkv, Sk, Dh)),
            "v_cache": _w((lambda *s: torch.randn(*s, dtype=torch.bfloat16) * 0.05)(B, Hkv, Sk, Dh)),
            "wq": _w((lambda *s: torch.randn(*s, dtype=torch.bfloat16) * 0.8)(D, Hq * Dh) * (D ** -0.5)),
            "wo": _w((lambda *s: torch.randn(*s, dtype=torch.bfloat16) * 0.05)(Hq * Dh, D) * ((Hq * Dh) ** -0.5)),
        }
    _A_in = _A_setup()

    def _B_setup():
        B, Sq, D = 2, 1, 448
        Hq, Hkv, Sk, Dh = 16, 8, 4096, 256
        assert Hq % Hkv == 0, (Hq, Hkv)
        return {
            "x": _w((lambda *s: torch.randn(*s, dtype=torch.bfloat16) * 0.8)(B, Sq, D)),
            "k_cache": _w((lambda *s: torch.randn(*s, dtype=torch.bfloat16) * 0.8)(B, Hkv, Sk, Dh)),
            "v_cache": _w((lambda *s: torch.randn(*s, dtype=torch.bfloat16) * 0.05)(B, Hkv, Sk, Dh)),
            "wq": _w((lambda *s: torch.randn(*s, dtype=torch.bfloat16) * 0.8)(D, Hq * Dh) * (D ** -0.5)),
            "wo": _w((lambda *s: torch.randn(*s, dtype=torch.bfloat16) * 0.05)(Hq * Dh, D) * ((Hq * Dh) ** -0.5)),
        }
    _B_in = _B_setup()

    return {
        "A_x": _A_in["x"],
        "A_k_cache": _A_in["k_cache"],
        "A_v_cache": _A_in["v_cache"],
        "A_wq": _A_in["wq"],
        "A_wo": _A_in["wo"],
        "B_x": _B_in["x"],
        "B_k_cache": _B_in["k_cache"],
        "B_v_cache": _B_in["v_cache"],
        "B_wq": _B_in["wq"],
        "B_wo": _B_in["wo"],
    }

def reference(A_x, A_k_cache, A_v_cache, A_wq, A_wo, B_x, B_k_cache, B_v_cache, B_wq, B_wo):
    def _A_ref(x, k_cache, v_cache, wq, wo):
        B, Sq, D = x.shape
        Hq, Dh = 16, 256
        Hkv = k_cache.shape[1]
        rep = Hq // Hkv
        q = (lambda x, *d: x.permute(*d))((x @ wq).reshape(B, Sq, Hq, Dh), 0, 2, 1, 3)
        k = (lambda x, n, axis: torch.repeat_interleave(x, n, dim=axis))(k_cache, rep, axis=1)
        v = (lambda x, n, axis: torch.repeat_interleave(x, n, dim=axis))(v_cache, rep, axis=1)
        scores = torch.einsum("bhqd,bhkd->bhqk", q, k) * (Dh ** -0.5)
        p = _softmax(scores, axis=-1)
        o = torch.einsum("bhqk,bhkd->bhqd", p, v)
        return (lambda x, *d: x.permute(*d))(o, 0, 2, 1, 3).reshape(B, Sq, Hq * Dh) @ wo

    def _B_ref(x, k_cache, v_cache, wq, wo):
        B, Sq, D = x.shape
        Hq, Dh = 16, 256
        Hkv = k_cache.shape[1]
        rep = Hq // Hkv
        q = (lambda x, *d: x.permute(*d))((x @ wq).reshape(B, Sq, Hq, Dh), 0, 2, 1, 3)
        k = (lambda x, n, axis: torch.repeat_interleave(x, n, dim=axis))(k_cache, rep, axis=1)
        v = (lambda x, n, axis: torch.repeat_interleave(x, n, dim=axis))(v_cache, rep, axis=1)
        scores = torch.einsum("bhqd,bhkd->bhqk", q, k) * (Dh ** -0.5)
        p = _softmax(scores, axis=-1)
        o = torch.einsum("bhqk,bhkd->bhqd", p, v)
        return (lambda x, *d: x.permute(*d))(o, 0, 2, 1, 3).reshape(B, Sq, Hq * Dh) @ wo

    a = _A_ref(A_x, A_k_cache, A_v_cache, A_wq, A_wo)
    b = _B_ref(B_x, B_k_cache, B_v_cache, B_wq, B_wo)
    return torch.concatenate([a, b], axis=-1)
```

```cpp
#include <cuda_runtime.h>
#include <cuda_bf16.h>
#include <cuda.h>
#include <stdint.h>

namespace {

constexpr int kD = 448;
constexpr int NCTA = 128;
constexpr int NCONS = 256;
constexpr int NTHREADS = NCONS + 64;
constexpr int LAG = 5, HOR = 8;
constexpr int NCHK = 5;
constexpr int TILE_BYTES = 32768;
constexpr int NT = 16;
constexpr int RING = 5;
constexpr int DEPTH = 2;
constexpr int W_HALF = 28672;
constexpr int HS = 1028;
constexpr int PP = 1032;
constexpr int XP = 456;
constexpr int QP = 264;
constexpr int OP = 72;

constexpr int OFF_RING = 0;
constexpr int OFF_W = OFF_RING + RING * TILE_BYTES;
constexpr int W_BYTES = 2 * W_HALF;
constexpr int OFF_S = OFF_W;
constexpr int OFF_P = OFF_W + W_BYTES;
constexpr int OFF_X = OFF_P + 2 * PP * 2;
constexpr int OFF_Q = OFF_X + 2 * XP * 2;
constexpr int OFF_O = OFF_Q + 2 * QP * 2;
constexpr int OFF_RED = OFF_O + 2 * OP * 2;
constexpr int OFF_WM = OFF_RED + 8 * 16 * 4;
constexpr int OFF_DUE = OFF_WM + 20 * 4;
constexpr int OFF_BAR = OFF_DUE + 36 * 4;
constexpr int SMEM_BYTES = OFF_BAR + (2 * RING + 4) * 8 + 1024;
static_assert(OFF_W % 16 == 0 && OFF_S % 16 == 0 && OFF_P % 16 == 0 && OFF_X % 16 == 0 && OFF_Q % 16 == 0 &&
              OFF_O % 16 == 0 && OFF_RED % 16 == 0 && OFF_BAR % 8 == 0, "align");
static_assert(4 * HS * 4 <= W_BYTES, "W region");
static_assert(SMEM_BYTES <= 232448, "smem");

struct Params {
    CUtensorMap map[2][4];
    const __nv_bfloat16* x[2];
    __nv_bfloat16* out;
    int pace, off, stag, pmin, pmax, lstar, e1;
};

__device__ __align__(128) unsigned long long g_x0[16 * 512];
__device__ __align__(128) unsigned long long g_xml[32 * 16];
__device__ __align__(128) unsigned long long g_x1[16 * 8 * 256];
__device__ __align__(128) unsigned long long g_x2[2 * 56 * 64 * 8];
__device__ __align__(128) unsigned long long g_ctl[NCHK * 32 * 4];
__device__ unsigned int g_epoch[NCTA];

#define STAMP(i) do { } while (0)

__device__ __forceinline__ unsigned long long gtime() {
    unsigned long long t; asm volatile("mov.u64 %0, %%globaltimer;" : "=l"(t)); return t;
}
__device__ __forceinline__ void mbar_init(uint32_t a, uint32_t c) {
    asm volatile("mbarrier.init.shared::cta.b64 [%0], %1;" ::"r"(a), "r"(c) : "memory");
}
__device__ __forceinline__ void mbar_expect_tx(uint32_t a, uint32_t b) {
    asm volatile("mbarrier.arrive.expect_tx.shared::cta.b64 _, [%0], %1;" ::"r"(a), "r"(b) : "memory");
}
__device__ __forceinline__ void mbar_arrive(uint32_t a) {
    asm volatile("mbarrier.arrive.shared::cta.b64 _, [%0];" ::"r"(a) : "memory");
}
__device__ __forceinline__ void mbar_wait(uint32_t a, uint32_t parity) {
    uint32_t done;
#pragma unroll 1
    for (int it = 0; it < (1 << 22); ++it) {
        asm volatile("{\n.reg .pred p;\nmbarrier.try_wait.parity.shared::cta.b64 p, [%1], %2;\nselp.u32 %0,1,0,p;\n}"
                     : "=r"(done) : "r"(a), "r"(parity) : "memory");
        if (done) return;
    }
    __trap();
}
__device__ __forceinline__ void bulk_load(uint32_t dst, const void* src, uint32_t bytes, uint32_t bar, uint64_t pol) {
    asm volatile("cp.async.bulk.shared::cluster.global.mbarrier::complete_tx::bytes.L2::cache_hint [%0], [%1], %2, [%3], %4;"
                 ::"r"(dst), "l"(src), "r"(bytes), "r"(bar), "l"(pol) : "memory");
}
__device__ __forceinline__ void tma3(uint32_t dst, const CUtensorMap* m, int row, uint32_t bar, uint64_t pol) {
    asm volatile("cp.async.bulk.tensor.3d.shared::cluster.global.mbarrier::complete_tx::bytes.L2::cache_hint [%0], [%1, {%3, %4, %3}], [%2], %5;"
                 ::"r"(dst), "l"(m), "r"(bar), "r"(0), "r"(row), "l"(pol) : "memory");
}
__device__ __forceinline__ void tma2(uint32_t dst, const CUtensorMap* m, int col, int row, uint32_t bar, uint64_t pol) {
    asm volatile("cp.async.bulk.tensor.2d.shared::cluster.global.mbarrier::complete_tx::bytes.L2::cache_hint [%0], [%1, {%3, %4}], [%2], %5;"
                 ::"r"(dst), "l"(m), "r"(bar), "r"(col), "r"(row), "l"(pol) : "memory");
}
__device__ __forceinline__ void ldsm4(uint32_t (&r)[4], uint32_t a) {
    asm volatile("ldmatrix.sync.aligned.m8n8.x4.shared.b16 {%0,%1,%2,%3}, [%4];"
                 : "=r"(r[0]), "=r"(r[1]), "=r"(r[2]), "=r"(r[3]) : "r"(a) : "memory");
}
__device__ __forceinline__ void ldsm4t(uint32_t (&r)[4], uint32_t a) {
    asm volatile("ldmatrix.sync.aligned.m8n8.x4.trans.shared.b16 {%0,%1,%2,%3}, [%4];"
                 : "=r"(r[0]), "=r"(r[1]), "=r"(r[2]), "=r"(r[3]) : "r"(a) : "memory");
}
__device__ __forceinline__ void mma16816(float (&c)[4], const uint32_t (&a)[4], uint32_t b0, uint32_t b1) {
    asm volatile("mma.sync.aligned.m16n8k16.row.col.f32.bf16.bf16.f32 {%0,%1,%2,%3}, {%4,%5,%6,%7}, {%8,%9}, {%0,%1,%2,%3};"
                 : "+f"(c[0]), "+f"(c[1]), "+f"(c[2]), "+f"(c[3])
                 : "r"(a[0]), "r"(a[1]), "r"(a[2]), "r"(a[3]), "r"(b0), "r"(b1));
}
__device__ __forceinline__ uint32_t lds32(uint32_t a) {
    uint32_t v; asm volatile("ld.shared.u32 %0, [%1];" : "=r"(v) : "r"(a) : "memory"); return v;
}
__device__ __forceinline__ uint4 lds128(uint32_t a) {
    uint4 v; asm volatile("ld.shared.v4.u32 {%0,%1,%2,%3}, [%4];" : "=r"(v.x), "=r"(v.y), "=r"(v.z), "=r"(v.w) : "r"(a) : "memory"); return v;
}
__device__ __forceinline__ void sts32(uint32_t a, uint32_t v) { asm volatile("st.shared.u32 [%0], %1;" ::"r"(a), "r"(v) : "memory"); }
__device__ __forceinline__ void sts128(uint32_t a, uint4 v) {
    asm volatile("st.shared.v4.u32 [%0], {%1,%2,%3,%4};" ::"r"(a), "r"(v.x), "r"(v.y), "r"(v.z), "r"(v.w) : "memory");
}
__device__ __forceinline__ void cons_sync() { asm volatile("bar.sync 1, 256;" ::: "memory"); }
__device__ __forceinline__ void put64(unsigned long long* p, unsigned long long v) {
    asm volatile("st.relaxed.gpu.global.u64 [%0], %1;" ::"l"(p), "l"(v) : "memory");
}
__device__ __forceinline__ void put(unsigned long long* p, uint32_t payload, uint32_t tag) {
    put64(p, ((unsigned long long)tag << 32) | payload);
}
constexpr unsigned long long kTagMask = 0x0000000F0000000FULL;
__device__ __forceinline__ void putff(unsigned long long* p, float a, float b, unsigned long long tagm) {
    const unsigned long long v = ((unsigned long long)__float_as_uint(b) << 32) | __float_as_uint(a);
    put64(p, (v & ~kTagMask) | tagm);
}
__device__ __forceinline__ bool okff(unsigned long long v, unsigned long long tagm) { return (v & kTagMask) == tagm; }
__device__ __forceinline__ bool ok8(const ulonglong2& a, const ulonglong2& b, const ulonglong2& c, const ulonglong2& d, unsigned long long tagm) {
    return ((((a.x ^ tagm) | (a.y ^ tagm) | (b.x ^ tagm) | (b.y ^ tagm)) | ((c.x ^ tagm) | (c.y ^ tagm) | (d.x ^ tagm) | (d.y ^ tagm))) & kTagMask) == 0;
}
__device__ __forceinline__ ulonglong2 get2p(const unsigned long long* p, int live) {
    ulonglong2 v = make_ulonglong2(0ULL, 0ULL);
    asm volatile("{\n.reg .pred p;\nsetp.ne.u32 p, %3, 0;\n@p ld.relaxed.gpu.global.v2.u64 {%0,%1}, [%2];\n}"
                 : "+l"(v.x), "+l"(v.y) : "l"(p), "r"(live) : "memory");
    return v;
}
__device__ __forceinline__ float flo(unsigned long long v) { return __uint_as_float((uint32_t)v & ~0xFu); }
__device__ __forceinline__ float fhi(unsigned long long v) { return __uint_as_float((uint32_t)(v >> 32) & ~0xFu); }
__device__ __forceinline__ unsigned long long get1(const unsigned long long* p) {
    unsigned long long v;
    asm volatile("ld.relaxed.gpu.global.u64 %0, [%1];" : "=l"(v) : "l"(p) : "memory");
    return v;
}
__device__ __forceinline__ ulonglong2 get2(const unsigned long long* p) {
    ulonglong2 v;
    asm volatile("ld.relaxed.gpu.global.v2.u64 {%0,%1}, [%2];" : "=l"(v.x), "=l"(v.y) : "l"(p) : "memory");
    return v;
}
__device__ __forceinline__ uint32_t hi32(unsigned long long v) { return (uint32_t)(v >> 32); }
__device__ __forceinline__ uint32_t pack_bf16(float lo, float hi) {
    __nv_bfloat162 h = __floats2bfloat162_rn(lo, hi);
    return *reinterpret_cast<uint32_t*>(&h);
}
__device__ __forceinline__ float sel4(const float (&c)[4], int t) {
    float a = (t & 1) ? c[1] : c[0];
    float b = (t & 1) ? c[3] : c[2];
    return (t & 2) ? b : a;
}
constexpr int SPIN_LIMIT = 1 << 21;

__global__ void __launch_bounds__(NTHREADS, 1) fused_decode_kernel(const __grid_constant__ Params prm) {
    extern __shared__ __align__(128) unsigned char smem[];
    const uint32_t sb = ((uint32_t)__cvta_generic_to_shared(smem) + 1023u) & ~1023u;
    const int tid = threadIdx.x, warp = tid >> 5, lane = tid & 31;
    const int bid = blockIdx.x;
    const int br = bid >> 6, hkv = (bid >> 3) & 7, jo = bid & 7, bb = jo >> 2, sp = jo & 3;
    const int octet = bid >> 3;
    const uint32_t bar_full = sb + OFF_BAR, bar_empty = bar_full + RING * 8, bar_w = bar_empty + RING * 8, bar_wo = bar_w + 16;

    uint64_t pol;
    asm volatile("createpolicy.fractional.L2::evict_first.b64 %0, 1.0;" : "=l"(pol));

    const unsigned long long t0 = gtime();
    if (tid == NCONS) {
        mbar_init(bar_w, 1); mbar_init(bar_w + 8, 1);
        asm volatile("fence.proxy.async.shared::cta;" ::: "memory");
        const int col = hkv * 512 + jo * 64;
        mbar_expect_tx(bar_w, W_HALF + 4 * kD);
        tma2(sb + OFF_W, &prm.map[br][2], col, 0, bar_w, pol);
        bulk_load(sb + OFF_X, prm.x[br], 2 * kD, bar_w, pol);
        bulk_load(sb + OFF_X + XP * 2, prm.x[br] + kD, 2 * kD, bar_w, pol);
        mbar_expect_tx(bar_w + 8, W_HALF);
        tma2(sb + OFF_W + W_HALF, &prm.map[br][2], col, 224, bar_w + 8, pol);
#pragma unroll
        for (int s = 0; s < RING; s++) { mbar_init(bar_full + s * 8, 1); mbar_init(bar_empty + s * 8, 8); }
        mbar_init(bar_wo, 1); mbar_init(bar_wo + 8, 1);
        asm volatile("fence.mbarrier_init.release.cluster;" ::: "memory");
        asm volatile("fence.proxy.async.shared::cta;" ::: "memory");
    }

    if (warp == 8) {
        __syncthreads();
        if (lane == 0) {
            const int row0 = (bb * 8 + hkv) * 4096 + sp * 1024;
            const unsigned long long base = t0 + prm.off + ((bid * prm.stag) >> 7);
            uint32_t tsum = 0;
#pragma unroll 1
            for (int i = 0; i < 2 * NT + 2; i++) {
                const int slot = i % RING;
                const int eoff = i == 2 * NT + 1 ? prm.e1 : 0;
                if (i >= DEPTH) {
                    const int w = i - DEPTH;
                    mbar_wait(bar_full + (w % RING) * 8, (w / RING) & 1);
                    tsum += (uint32_t)(gtime() - base);
                    if ((w & 3) == 3) {
                        if ((bid & 3) == 0 && w >= 7 && w < 7 + 4 * NCHK) {
                            const unsigned long long v = ((unsigned long long)lds32(sb + OFF_WM + 64) << 32) | (tsum >> 2);
                            unsigned long long* p = &g_ctl[(((w - 7) >> 2) * 32 + (bid >> 2)) * 4];
                            asm volatile("st.relaxed.gpu.global.v2.u64 [%0], {%1, %1};" ::"l"(p), "l"(v) : "memory");
                            asm volatile("st.relaxed.gpu.global.v2.u64 [%0], {%1, %1};" ::"l"(p + 2), "l"(v) : "memory");
                        }
                        tsum = 0;
                    }
                }
                if (i < 2 * NT && i >= RING) mbar_wait(bar_empty + slot * 8, ((i / RING) - 1) & 1);
                for (int it = 0; it < (1 << 16) && (int)((uint32_t)(gtime() - base) - lds32(sb + OFF_DUE + i * 4)) < eoff; ++it) { }
                if (i < 2 * NT) {
                    mbar_expect_tx(bar_full + slot * 8, TILE_BYTES);
                    tma3(sb + OFF_RING + slot * TILE_BYTES, &prm.map[br][i >= NT], row0 + (i & (NT - 1)) * 64, bar_full + slot * 8, pol);
                } else {
                    const int h = i - 2 * NT;
                    mbar_expect_tx(bar_wo + h * 8, W_HALF);
                    tma3(sb + OFF_W + h * W_HALF, &prm.map[br][3], hkv * 512 + jo * 64 + h * 32, bar_wo + h * 8, pol);
                }
            }
        }
        __syncwarp();
        {
            uint32_t tg;
            asm volatile("ld.shared.u32 %0, [%1];" : "=r"(tg) : "r"(sb + OFF_WM + 64) : "memory");
            const unsigned long long tagm = ((unsigned long long)(tg >> 4) << 32) | (tg & 15);
            const unsigned long long* p = &g_x1[((octet * 8 + jo) * 2 + (lane >> 4)) * 128 + (lane & 15) * 2];
            ulonglong2 v0, v1, v2, v3;
            int it = 0;
            do {
                v0 = get2(p); v1 = get2(p + 32); v2 = get2(p + 64); v3 = get2(p + 96);
                if (++it > SPIN_LIMIT) __trap();
            } while (!__all_sync(0xffffffffu, ok8(v0, v1, v2, v3, tagm)));
            const uint32_t oa = sb + OFF_O + (lane >> 4) * OP * 2 + (((lane & 15) >> 2) * 16 + (lane & 3) * 2) * 2;
            sts32(oa, pack_bf16((flo(v0.x) + flo(v1.x)) + (flo(v2.x) + flo(v3.x)), (flo(v0.y) + flo(v1.y)) + (flo(v2.y) + flo(v3.y))));
            sts32(oa + 16, pack_bf16((fhi(v0.x) + fhi(v1.x)) + (fhi(v2.x) + fhi(v3.x)), (fhi(v0.y) + fhi(v1.y)) + (fhi(v2.y) + fhi(v3.y))));
            if (lane == 0) STAMP(9);
            asm volatile("bar.arrive 2, 288;" ::: "memory");
        }
        return;
    }

    if (warp == 9) {
        sts32(sb + OFF_DUE + lane * 4, lane * prm.pace);
        if (lane < 4) sts32(sb + OFF_DUE + 128 + lane * 4, (32 + lane) * prm.pace);
        __syncthreads();
        asm volatile("bar.sync 3, 64;" ::: "memory");
        if (prm.pace == 0) return;
        const uint32_t tag = lds32(sb + OFF_WM + 64);
        const unsigned long long base = t0 + prm.off + ((bid * prm.stag) >> 7);
        float cap = (float)prm.pace, tprev = 0.f, nest = 1.f;
#pragma unroll 1
        for (int k = 0; k < NCHK; k++) {
            const int c = 7 + 4 * k, a = c + LAG;
            for (int it = 0; it < (1 << 12) && (int)((uint32_t)(gtime() - base) - lds32(sb + OFF_DUE + (c + 3) * 4)) < 0; ++it) __nanosleep(100);
            unsigned long long v;
            int it = 0;
            do { v = get1(&g_ctl[(k * 32 + lane) * 4]); if (++it > SPIN_LIMIT) __trap(); } while (!__all_sync(0xffffffffu, hi32(v) == tag));
            const float T = (float)__reduce_add_sync(0xffffffffu, (uint32_t)v) * (1.f / 32.f);
            bool jump = false;
            if (k > 0) {
                const float est = (T - tprev) * 0.25f;
                jump = est > cap * 1.047f;
                if (!jump) { nest += 1.f; cap += (est - cap) / nest; }
            }
            tprev = T;
            const float da = (float)lds32(sb + OFF_DUE + a * 4);
            const float err = T + (LAG + 1.5f) * cap - da - (float)prm.lstar;
            const float pn = jump ? cap : fminf(fmaxf(cap + err * (1.f / HOR), (float)prm.pmin), (float)prm.pmax);
            const float d0 = da + (jump ? fmaxf(err, 0.f) : 0.f);
            __syncwarp();
            if (a + lane < 36) sts32(sb + OFF_DUE + (a + lane) * 4, (uint32_t)(d0 + (float)lane * pn));
            __syncwarp();
        }
        return;
    }

    const int g = lane >> 2, t = lane & 3, mi = lane >> 3, r8 = lane & 7;
    const int grp = bid >> 2;
    unsigned long long* const px0 = &g_x0[octet * 512 + (t & 1) * 256 + jo * 32 + (warp & 3) * 8 + g];
    unsigned long long* const pxml = &g_xml[grp * 16 + sp * 4 + (lane & 3)];
    unsigned long long* const px1 = &g_x1[(((octet * 8 + (t & 1) * 4 + (warp >> 1)) * 2 + bb) * 4 + sp) * 32 + ((warp & 1) * 2 + (t >> 1)) * 8 + g];
    unsigned long long* const px2 = &g_x2[((size_t)(br * 56 + 2 * warp + (t & 1) + 16 * (t >> 1)) * 64 + (bid & 63)) * 8 + g];
    uint32_t tag;
    asm volatile("ld.relaxed.gpu.global.u32 %0, [%1];" : "=r"(tag) : "l"(&g_epoch[bid]) : "memory");
    if (warp < 4 && t < 2) put64(px0, 0);
    if (tid < 4) put64(pxml, 0);
    __syncthreads();
    tag = tag >= 255 ? 1 : tag + 1;
    const unsigned long long tagm = ((unsigned long long)(tag >> 4) << 32) | (tag & 15);

    if (warp < 4) {
        float c0[4] = {0.f, 0.f, 0.f, 0.f}, c1[4] = {0.f, 0.f, 0.f, 0.f};
        const uint32_t wa = sb + OFF_W + (8 * (mi >> 1) + r8) * 128 + ((2 * warp + (mi & 1)) ^ r8) * 16;
        const uint32_t xa = sb + OFF_X + (g & 1) * XP * 2 + t * 4;
#pragma unroll
        for (int h = 0; h < 2; h++) {
            mbar_wait(bar_w + h * 8, 0);
            if (tid == 0) STAMP(1 + h);
#pragma unroll
            for (int ks = h * 14; ks < h * 14 + 14; ks += 2) {
                uint32_t a0[4], a1[4];
                ldsm4t(a0, wa + ks * 2048);
                ldsm4t(a1, wa + (ks + 1) * 2048);
                const uint32_t b00 = lds32(xa + ks * 32), b01 = lds32(xa + ks * 32 + 16);
                const uint32_t b10 = lds32(xa + ks * 32 + 32), b11 = lds32(xa + ks * 32 + 48);
                mma16816(c0, a0, b00, b01);
                mma16816(c1, a1, b10, b11);
            }
        }
        const uint32_t pk = (t & 1) ? pack_bf16(c0[1] + c1[1], c0[3] + c1[3]) : pack_bf16(c0[0] + c1[0], c0[2] + c1[2]);
        if (t < 2) put(px0, pk, tag);
        if (tid == 0) STAMP(3);
    }
    {
        const unsigned long long* p = &g_x0[octet * 512 + bb * 256 + tid];
        unsigned long long v;
        int it = 0;
        if (warp >= 4) mbar_wait(bar_w + 8, 0);
        {
            const unsigned long long tw = gtime();
            for (int w = 0; w < 256 && gtime() - tw < (warp >= 4 ? 700u : 500u); ++w) { }
        }
        do { v = get1(p); if (++it > SPIN_LIMIT) __trap(); } while (!__all_sync(0xffffffffu, hi32(v) == tag));
        const uint32_t qa = sb + OFF_Q + (tid >> 7) * QP * 2 + (((tid & 127) >> 3) * 16 + (tid & 7)) * 2;
        asm volatile("st.shared.u16 [%0], %1;" ::"r"(qa), "h"((unsigned short)(v & 0xffff)) : "memory");
        asm volatile("st.shared.u16 [%0], %1;" ::"r"(qa + 16), "h"((unsigned short)((v >> 16) & 0xffff)) : "memory");
    }
    cons_sync();
    if (tid == 0) { g_epoch[bid] = tag; sts32(sb + OFF_WM + 64, tag); STAMP(4); }
    if (warp == 0) { __syncwarp(); asm volatile("bar.arrive 3, 64;" ::: "memory"); }

    {
        const int u = warp & 3, hf = warp >> 2;
        uint32_t qb[16];
        const uint32_t qa = sb + OFF_Q + (g & 1) * QP * 2 + hf * 256 + t * 4;
#pragma unroll
        for (int kk = 0; kk < 8; kk++) { qb[2 * kk] = lds32(qa + kk * 32); qb[2 * kk + 1] = lds32(qa + kk * 32 + 16); }
        const uint32_t ka = sb + OFF_RING + hf * 16384 + (16 * u + 8 * (mi & 1) + r8) * 128 + ((mi >> 1) ^ r8) * 16;
        const uint32_t sa = sb + OFF_S + ((hf * 2 + (t & 1)) * HS + (g >> 1) * 16 + u * 4 + (t >> 1) * 2 + (g & 1)) * 4;
#pragma unroll 1
        for (int i = 0; i < NT; i++) {
            const int slot = i % RING;
            mbar_wait(bar_full + slot * 8, (i / RING) & 1);
            float c0[4] = {0.f, 0.f, 0.f, 0.f}, c1[4] = {0.f, 0.f, 0.f, 0.f};
            uint32_t a[8][4];
#pragma unroll
            for (int kk = 0; kk < 8; kk++) ldsm4(a[kk], ((ka ^ ((kk & 3) * 32)) + (kk >> 2) * 8192) + slot * TILE_BYTES);
#pragma unroll
            for (int kk = 0; kk < 8; kk += 2) {
                mma16816(c0, a[kk], qb[2 * kk], qb[2 * kk + 1]);
                mma16816(c1, a[kk + 1], qb[2 * kk + 2], qb[2 * kk + 3]);
            }
            __syncwarp();
            if (lane == 0) mbar_arrive(bar_empty + slot * 8);
            sts32(sa + i * 256, __float_as_uint(sel4(c0, t) + sel4(c1, t)));
        }
    }
    cons_sync();
    if (tid == 0) STAMP(5);

    constexpr float kScale = 0.0625f * 1.4426950408889634f;
    {
        const int h = warp >> 2;
        const uint32_t a0 = sb + OFF_S + (h * HS + (tid & 127) * 8) * 4, a1 = a0 + 2 * HS * 4;
        const uint4 x0 = lds128(a0), x1 = lds128(a0 + 16), y0 = lds128(a1), y1 = lds128(a1 + 16);
        float s[8];
        s[0] = __uint_as_float(x0.x) + __uint_as_float(y0.x); s[1] = __uint_as_float(x0.y) + __uint_as_float(y0.y);
        s[2] = __uint_as_float(x0.z) + __uint_as_float(y0.z); s[3] = __uint_as_float(x0.w) + __uint_as_float(y0.w);
        s[4] = __uint_as_float(x1.x) + __uint_as_float(y1.x); s[5] = __uint_as_float(x1.y) + __uint_as_float(y1.y);
        s[6] = __uint_as_float(x1.z) + __uint_as_float(y1.z); s[7] = __uint_as_float(x1.w) + __uint_as_float(y1.w);
        float m = fmaxf(fmaxf(fmaxf(s[0], s[1]), fmaxf(s[2], s[3])), fmaxf(fmaxf(s[4], s[5]), fmaxf(s[6], s[7])));
#pragma unroll
        for (int o = 16; o > 0; o >>= 1) m = fmaxf(m, __shfl_xor_sync(0xffffffffu, m, o));
        if (lane == 0) sts32(sb + OFF_WM + warp * 4, __float_as_uint(m));
        cons_sync();
        const uint4 wm = lds128(sb + OFF_WM + h * 16);
        m = fmaxf(fmaxf(__uint_as_float(wm.x), __uint_as_float(wm.y)), fmaxf(__uint_as_float(wm.z), __uint_as_float(wm.w)));
        float l = 0.f;
#pragma unroll
        for (int e = 0; e < 8; e++) { s[e] = exp2f((s[e] - m) * kScale); l += s[e]; }
        sts128(sb + OFF_P + h * PP * 2 + (tid & 127) * 16,
               make_uint4(pack_bf16(s[0], s[1]), pack_bf16(s[2], s[3]), pack_bf16(s[4], s[5]), pack_bf16(s[6], s[7])));
#pragma unroll
        for (int o = 16; o > 0; o >>= 1) l += __shfl_xor_sync(0xffffffffu, l, o);
        if (lane == 0) sts32(sb + OFF_WM + 32 + warp * 4, __float_as_uint(l));
        cons_sync();
        if (tid < 4) {
            const uint4 wm2 = lds128(sb + OFF_WM + (tid & 1) * 16), wl = lds128(sb + OFF_WM + 32 + (tid & 1) * 16);
            const float mt = fmaxf(fmaxf(__uint_as_float(wm2.x), __uint_as_float(wm2.y)), fmaxf(__uint_as_float(wm2.z), __uint_as_float(wm2.w)));
            const float lt = (__uint_as_float(wl.x) + __uint_as_float(wl.y)) + (__uint_as_float(wl.z) + __uint_as_float(wl.w));
            put(pxml, __float_as_uint((tid & 2) ? lt : mt), tag);
        }
    }
    if (tid == 0) STAMP(6);

    float acc0[4] = {0.f, 0.f, 0.f, 0.f}, acc1[4] = {0.f, 0.f, 0.f, 0.f};
    float wgt = 0.f;
    const uint32_t va = sb + OFF_RING + (warp >> 1) * 8192 + (8 * (mi >> 1) + r8) * 128 + (((warp & 1) * 4 + (mi & 1)) ^ r8) * 16;
    const uint32_t pa = sb + OFF_P + (g & 1) * PP * 2 + t * 32;
    const uint32_t wa = sb + OFF_W + (warp >> 2) * 4096 + (8 * (mi >> 1) + r8) * 128 + ((((2 * warp) & 7) + (mi & 1)) ^ r8) * 16;
    const uint32_t oa = sb + OFF_O + (g & 1) * OP * 2 + t * 4;
    const int rr = bid & 63;
    const unsigned long long* const pr2 = &g_x2[(size_t)(br * 56 + rr) * 512 + tid * 2];
#pragma unroll 1
    for (int pass = 0; pass < 2; pass++) {
        int live;
        asm volatile("mov.u32 %0, %1;" : "=r"(live) : "r"(pass));
        const unsigned long long tg = live ? tagm : 0ULL;
#pragma unroll 1
        for (int i = 0; i < live * NT; i++) {
            const int n = NT + i, slot = n % RING;
            if (i == NT - 3) {
                const unsigned long long* p = &g_xml[grp * 16 + (lane & 15)];
                unsigned long long v;
                int it = 0;
                do { v = get1(p); if (++it > SPIN_LIMIT) __trap(); } while (!__all_sync(0xffffffffu, hi32(v) == tag));
                const float f = __uint_as_float((uint32_t)v);
                float ms[4], ls[4];
#pragma unroll
                for (int s = 0; s < 4; s++) {
                    ms[s] = __shfl_sync(0xffffffffu, f, s * 4 + (t & 1));
                    ls[s] = __shfl_sync(0xffffffffu, f, s * 4 + 2 + (t & 1));
                }
                const float mloc = __shfl_sync(0xffffffffu, f, sp * 4 + (t & 1));
                const float M = fmaxf(fmaxf(ms[0], ms[1]), fmaxf(ms[2], ms[3]));
                float L = 0.f;
#pragma unroll
                for (int s = 0; s < 4; s++) L += ls[s] * exp2f((ms[s] - M) * kScale);
                wgt = exp2f((mloc - M) * kScale) / L;
            }
            const uint4 p0 = lds128(pa + i * 128), p1 = lds128(pa + i * 128 + 16);
            mbar_wait(bar_full + slot * 8, (n / RING) & 1);
            if (tid == 0 && i == NT - 1) STAMP(7);
            uint32_t a[8][4];
#pragma unroll
            for (int j = 0; j < 4; j++) {
                ldsm4t(a[2 * j], va + slot * TILE_BYTES + j * 2048);
                ldsm4t(a[2 * j + 1], (va ^ 32) + slot * TILE_BYTES + j * 2048);
            }
            mma16816(acc0, a[0], p0.x, p0.y); mma16816(acc1, a[1], p0.x, p0.y);
            mma16816(acc0, a[2], p0.z, p0.w); mma16816(acc1, a[3], p0.z, p0.w);
            mma16816(acc0, a[4], p1.x, p1.y); mma16816(acc1, a[5], p1.x, p1.y);
            mma16816(acc0, a[6], p1.z, p1.w); mma16816(acc1, a[7], p1.z, p1.w);
            __syncwarp();
            if (lane == 0) mbar_arrive(bar_empty + slot * 8);
        }
        {
            const float a0 = (t & 2) ? acc1[0] : acc0[0], a1 = (t & 2) ? acc1[1] : acc0[1];
            const float a2 = (t & 2) ? acc1[2] : acc0[2], a3 = (t & 2) ? acc1[3] : acc0[3];
            putff(px1, ((t & 1) ? a1 : a0) * wgt, ((t & 1) ? a3 : a2) * wgt, tg);
        }
        if (tid == 0) STAMP(8);
        {
            uint32_t a[4][2][4];
            float c[4][4];
            uint32_t ob[8];
#pragma unroll
            for (int m = 0; m < 4; m++) { c[m][0] = c[m][1] = c[m][2] = c[m][3] = 0.f; }
            if (live) mbar_wait(bar_wo, 0);
#pragma unroll
            for (int m = 0; m < 4; m++)
                if (m < 3 || warp < 4) { ldsm4t(a[m][0], wa + m * 8192); ldsm4t(a[m][1], wa + m * 8192 + 2048); }
            if (live) asm volatile("bar.sync 2, 288;" ::: "memory");
#pragma unroll
            for (int ks = 0; ks < 4; ks++) { ob[2 * ks] = lds32(oa + ks * 32); ob[2 * ks + 1] = lds32(oa + ks * 32 + 16); }
#pragma unroll
            for (int ks = 0; ks < 2; ks++)
#pragma unroll
                for (int m = 0; m < 4; m++)
                    if (m < 3 || warp < 4) mma16816(c[m], a[m][ks], ob[2 * ks], ob[2 * ks + 1]);
            if (live) mbar_wait(bar_wo + 8, 0);
            if (tid == 0) STAMP(10);
#pragma unroll
            for (int m = 0; m < 4; m++)
                if (m < 3 || warp < 4) { ldsm4t(a[m][0], wa + W_HALF + m * 8192); ldsm4t(a[m][1], wa + W_HALF + m * 8192 + 2048); }
#pragma unroll
            for (int ks = 0; ks < 2; ks++)
#pragma unroll
                for (int m = 0; m < 4; m++)
                    if (m < 3 || warp < 4) mma16816(c[m], a[m][ks], ob[4 + 2 * ks], ob[5 + 2 * ks]);
            {
                const float a0 = (t & 2) ? c[1][0] : c[0][0], a1 = (t & 2) ? c[1][1] : c[0][1];
                const float a2 = (t & 2) ? c[1][2] : c[0][2], a3 = (t & 2) ? c[1][3] : c[0][3];
                putff(px2, (t & 1) ? a2 : a0, (t & 1) ? a3 : a1, tg);
            }
            if (warp < 4 || t < 2) {
                const float a0 = (t & 2) ? c[3][0] : c[2][0], a1 = (t & 2) ? c[3][1] : c[2][1];
                const float a2 = (t & 2) ? c[3][2] : c[2][2], a3 = (t & 2) ? c[3][3] : c[2][3];
                putff(px2 + 32 * 64 * 8, (t & 1) ? a2 : a0, (t & 1) ? a3 : a1, tg);
            }
        }
        if (tid == 0) STAMP(11);
        if (rr < 56) {
            ulonglong2 v;
            int it = 0;
            do {
                v = get2p(pr2, live);
                if (++it > SPIN_LIMIT) __trap();
            } while (!__all_sync(0xffffffffu, okff(v.x, tg) && okff(v.y, tg)));
            if (tid == 0) STAMP(13);
            float s0 = flo(v.x), s1 = fhi(v.x), s2 = flo(v.y), s3 = fhi(v.y);
#pragma unroll
            for (int o = 4; o < 32; o <<= 1) {
                s0 += __shfl_xor_sync(0xffffffffu, s0, o); s1 += __shfl_xor_sync(0xffffffffu, s1, o);
                s2 += __shfl_xor_sync(0xffffffffu, s2, o); s3 += __shfl_xor_sync(0xffffffffu, s3, o);
            }
            if (lane < 16) {
                const float lo = (lane & 8) ? s1 : s0, hi = (lane & 8) ? s3 : s2;
                sts32(sb + OFF_RED + (warp * 16 + (lane & 8) + (lane & 3) * 2 + ((lane >> 2) & 1)) * 4, __float_as_uint((lane & 4) ? hi : lo));
            }
            cons_sync();
            if (tid < 16) {
                float f[8];
#pragma unroll
                for (int w = 0; w < 8; w++) f[w] = __uint_as_float(lds32(sb + OFF_RED + (w * 16 + tid) * 4));
                const float o = ((f[0] + f[1]) + (f[2] + f[3])) + ((f[4] + f[5]) + (f[6] + f[7]));
                if (live) prm.out[(tid >> 3) * (2 * kD) + br * kD + rr * 8 + (tid & 7)] = __float2bfloat16_rn(o);
            }
        }
        if (tid == 0) STAMP(12);
    }
}

}

typedef CUresult (*EncodeTiledFn)(CUtensorMap*, CUtensorMapDataType, cuuint32_t, void*, const cuuint64_t*, const cuuint64_t*,
                                  const cuuint32_t*, const cuuint32_t*, CUtensorMapInterleave, CUtensorMapSwizzle,
                                  CUtensorMapL2promotion, CUtensorMapFloatOOBfill);

extern "C" void kernel_launch(void* const* d_in, const int* in_sizes, int n_in, void* d_out, int out_size) {
    (void)in_sizes; (void)n_in; (void)out_size;
    static EncodeTiledFn enc = nullptr;
    static double unit_ns = 0.0;
    if (!enc) {
        int dev = 0, khz = 0, bits = 0;
        cudaGetDevice(&dev);
        if (cudaDeviceGetAttribute(&khz, cudaDevAttrMemoryClockRate, dev) == cudaSuccess &&
            cudaDeviceGetAttribute(&bits, cudaDevAttrGlobalMemoryBusWidth, dev) == cudaSuccess && khz > 0 && bits > 0)
            unit_ns = (double)NCTA * TILE_BYTES / (2.0 * khz * 1e-6 * bits / 8.0);
        (void)cudaGetLastError();
        cudaDriverEntryPointQueryResult qr;
        cudaGetDriverEntryPoint("cuTensorMapEncodeTiled", (void**)&enc, cudaEnableDefault, &qr);
        cudaFuncSetAttribute(fused_decode_kernel, cudaFuncAttributeMaxDynamicSharedMemorySize, SMEM_BYTES);
    }
    Params p;
    const cuuint32_t es[3] = {1, 1, 1};
    for (int b = 0; b < 2; b++) {
        p.x[b] = (const __nv_bfloat16*)d_in[b * 5 + 0];
        for (int kv = 0; kv < 2; kv++) {
            const cuuint64_t gd[3] = {64, 65536, 4}, gs[2] = {512, 128};
            const cuuint32_t bd[3] = {64, 64, 4};
            enc(&p.map[b][kv], CU_TENSOR_MAP_DATA_TYPE_BFLOAT16, 3, d_in[b * 5 + 1 + kv], gd, gs, bd, es, CU_TENSOR_MAP_INTERLEAVE_NONE,
                CU_TENSOR_MAP_SWIZZLE_128B, CU_TENSOR_MAP_L2_PROMOTION_L2_256B, CU_TENSOR_MAP_FLOAT_OOB_FILL_NONE);
        }
        {
            const cuuint64_t gd[2] = {4096, 448}, gs[1] = {8192};
            const cuuint32_t bd[2] = {64, 224};
            enc(&p.map[b][2], CU_TENSOR_MAP_DATA_TYPE_BFLOAT16, 2, d_in[b * 5 + 3], gd, gs, bd, es, CU_TENSOR_MAP_INTERLEAVE_NONE,
                CU_TENSOR_MAP_SWIZZLE_128B, CU_TENSOR_MAP_L2_PROMOTION_L2_256B, CU_TENSOR_MAP_FLOAT_OOB_FILL_NONE);
        }
        {
            const cuuint64_t gd[3] = {64, 4096, 7}, gs[2] = {896, 128};
            const cuuint32_t bd[3] = {64, 32, 7};
            enc(&p.map[b][3], CU_TENSOR_MAP_DATA_TYPE_BFLOAT16, 3, d_in[b * 5 + 4], gd, gs, bd, es, CU_TENSOR_MAP_INTERLEAVE_NONE,
                CU_TENSOR_MAP_SWIZZLE_128B, CU_TENSOR_MAP_L2_PROMOTION_L2_256B, CU_TENSOR_MAP_FLOAT_OOB_FILL_NONE);
        }
    }
    p.out = (__nv_bfloat16*)d_out;
    const double u = unit_ns;
    p.pace = (int)(u * 1.031); p.pmin = (int)(u * 1.009); p.pmax = (int)(u * 1.071);
    p.off = (int)(u * 1.28); p.stag = (int)(u * 0.64); p.lstar = (int)(u * 1.48); p.e1 = (int)(u * 0.12);
    fused_decode_kernel<<<NCTA, NTHREADS, SMEM_BYTES>>>(p);
}
```

```cpp
#include <cuda_runtime.h>
#include <cuda_bf16.h>
#include <cuda.h>
#include <stdint.h>

namespace {

constexpr int kD = 448;
constexpr int NCTA = 128;
constexpr int NCONS = 256;
constexpr int NTHREADS = NCONS + 64 + 256;
constexpr int LAG = 5, HOR = 8;
constexpr int NCHK = 5;
constexpr int TILE_BYTES = 32768;
constexpr int NT = 16;
constexpr int NSWEEP = 14;
constexpr int RING = 5;
constexpr int DEPTH = 2;
constexpr int W_HALF = 28672;
constexpr int HS = 1028;
constexpr int PP = 1032;
constexpr int XP = 456;
constexpr int QP = 264;
constexpr int OP = 72;

constexpr int OFF_RING = 0;
constexpr int OFF_W = OFF_RING + RING * TILE_BYTES;
constexpr int W_BYTES = 2 * W_HALF;
constexpr int OFF_S = OFF_W;
constexpr int OFF_QA = OFF_S + 2 * HS * 4;
constexpr int OFF_P = OFF_W + W_BYTES;
constexpr int OFF_X = OFF_P + 2 * PP * 2;
constexpr int OFF_O = OFF_X + 2 * XP * 2;
constexpr int OFF_RED = OFF_O + 2 * OP * 2;
constexpr int OFF_WM = OFF_RED + 8 * 16 * 4;
constexpr int OFF_TAG = OFF_WM + 64;
constexpr int OFF_DUE = OFF_TAG + 16;
constexpr int OFF_BAR = OFF_DUE + 36 * 4;
constexpr int SMEM_BYTES = OFF_BAR + (2 * RING + 5) * 8 + 1024;
static_assert(OFF_W % 16 == 0 && OFF_S % 16 == 0 && OFF_P % 16 == 0 && OFF_X % 16 == 0 && OFF_QA % 16 == 0 &&
              OFF_O % 16 == 0 && OFF_RED % 16 == 0 && OFF_BAR % 8 == 0, "align");
static_assert(OFF_QA + 32 * QP * 2 <= OFF_W + W_BYTES, "W region");
static_assert(SMEM_BYTES <= 232448, "smem");

struct Params {
    CUtensorMap map[2][4];
    const __nv_bfloat16* x[2];
    __nv_bfloat16* out;
    int pace, off, stag, pmin, pmax, lstar, e1;
};

__device__ __align__(128) unsigned long long g_x0[16 * 512];
__device__ __align__(128) unsigned long long g_xml[32 * 16];
__device__ __align__(128) unsigned long long g_x1[16 * 8 * 256];
__device__ __align__(128) unsigned long long g_x2[2 * 56 * 64 * 8];
__device__ __align__(128) unsigned long long g_ctl[NCHK * 32 * 4];
__device__ __align__(128) unsigned long long g_xs[NCTA * NSWEEP * 64];
__device__ unsigned int g_epoch[NCTA];

__device__ __forceinline__ unsigned long long gtime() {
    unsigned long long t; asm volatile("mov.u64 %0, %%globaltimer;" : "=l"(t)); return t;
}
__device__ __forceinline__ void mbar_init(uint32_t a, uint32_t c) {
    asm volatile("mbarrier.init.shared::cta.b64 [%0], %1;" ::"r"(a), "r"(c) : "memory");
}
__device__ __forceinline__ void mbar_expect_tx(uint32_t a, uint32_t b) {
    asm volatile("mbarrier.arrive.expect_tx.shared::cta.b64 _, [%0], %1;" ::"r"(a), "r"(b) : "memory");
}
__device__ __forceinline__ void mbar_arrive(uint32_t a) {
    asm volatile("mbarrier.arrive.shared::cta.b64 _, [%0];" ::"r"(a) : "memory");
}
__device__ __forceinline__ void mbar_wait(uint32_t a, uint32_t parity) {
    uint32_t done;
#pragma unroll 1
    for (int it = 0; it < (1 << 22); ++it) {
        asm volatile("{\n.reg .pred p;\nmbarrier.try_wait.parity.shared::cta.b64 p, [%1], %2;\nselp.u32 %0,1,0,p;\n}"
                     : "=r"(done) : "r"(a), "r"(parity) : "memory");
        if (done) return;
    }
    __trap();
}
__device__ __forceinline__ void bulk_load(uint32_t dst, const void* src, uint32_t bytes, uint32_t bar, uint64_t pol) {
    asm volatile("cp.async.bulk.shared::cluster.global.mbarrier::complete_tx::bytes.L2::cache_hint [%0], [%1], %2, [%3], %4;"
                 ::"r"(dst), "l"(src), "r"(bytes), "r"(bar), "l"(pol) : "memory");
}
__device__ __forceinline__ void tma3(uint32_t dst, const CUtensorMap* m, int row, uint32_t bar, uint64_t pol) {
    asm volatile("cp.async.bulk.tensor.3d.shared::cluster.global.mbarrier::complete_tx::bytes.L2::cache_hint [%0], [%1, {%3, %4, %3}], [%2], %5;"
                 ::"r"(dst), "l"(m), "r"(bar), "r"(0), "r"(row), "l"(pol) : "memory");
}
__device__ __forceinline__ void tma2(uint32_t dst, const CUtensorMap* m, int col, int row, uint32_t bar, uint64_t pol) {
    asm volatile("cp.async.bulk.tensor.2d.shared::cluster.global.mbarrier::complete_tx::bytes.L2::cache_hint [%0], [%1, {%3, %4}], [%2], %5;"
                 ::"r"(dst), "l"(m), "r"(bar), "r"(col), "r"(row), "l"(pol) : "memory");
}
__device__ __forceinline__ void ldsm4(uint32_t (&r)[4], uint32_t a) {
    asm volatile("ldmatrix.sync.aligned.m8n8.x4.shared.b16 {%0,%1,%2,%3}, [%4];"
                 : "=r"(r[0]), "=r"(r[1]), "=r"(r[2]), "=r"(r[3]) : "r"(a) : "memory");
}
__device__ __forceinline__ void ldsm4t(uint32_t (&r)[4], uint32_t a) {
    asm volatile("ldmatrix.sync.aligned.m8n8.x4.trans.shared.b16 {%0,%1,%2,%3}, [%4];"
                 : "=r"(r[0]), "=r"(r[1]), "=r"(r[2]), "=r"(r[3]) : "r"(a) : "memory");
}
__device__ __forceinline__ void mma16816(float (&c)[4], const uint32_t (&a)[4], uint32_t b0, uint32_t b1) {
    asm volatile("mma.sync.aligned.m16n8k16.row.col.f32.bf16.bf16.f32 {%0,%1,%2,%3}, {%4,%5,%6,%7}, {%8,%9}, {%0,%1,%2,%3};"
                 : "+f"(c[0]), "+f"(c[1]), "+f"(c[2]), "+f"(c[3])
                 : "r"(a[0]), "r"(a[1]), "r"(a[2]), "r"(a[3]), "r"(b0), "r"(b1));
}
__device__ __forceinline__ uint32_t lds32(uint32_t a) {
    uint32_t v; asm volatile("ld.shared.u32 %0, [%1];" : "=r"(v) : "r"(a) : "memory"); return v;
}
__device__ __forceinline__ uint4 lds128(uint32_t a) {
    uint4 v; asm volatile("ld.shared.v4.u32 {%0,%1,%2,%3}, [%4];" : "=r"(v.x), "=r"(v.y), "=r"(v.z), "=r"(v.w) : "r"(a) : "memory"); return v;
}
__device__ __forceinline__ void sts32(uint32_t a, uint32_t v) { asm volatile("st.shared.u32 [%0], %1;" ::"r"(a), "r"(v) : "memory"); }
__device__ __forceinline__ void sts128(uint32_t a, uint4 v) {
    asm volatile("st.shared.v4.u32 [%0], {%1,%2,%3,%4};" ::"r"(a), "r"(v.x), "r"(v.y), "r"(v.z), "r"(v.w) : "memory");
}
__device__ __forceinline__ void cons_sync() { asm volatile("bar.sync 1, 256;" ::: "memory"); }
__device__ __forceinline__ void put64(unsigned long long* p, unsigned long long v) {
    asm volatile("st.relaxed.gpu.global.u64 [%0], %1;" ::"l"(p), "l"(v) : "memory");
}
__device__ __forceinline__ void put(unsigned long long* p, uint32_t payload, uint32_t tag) {
    put64(p, ((unsigned long long)tag << 32) | payload);
}
constexpr unsigned long long kTagMask = 0x0000000F0000000FULL;
__device__ __forceinline__ void putff(unsigned long long* p, float a, float b, unsigned long long tagm) {
    const unsigned long long v = ((unsigned long long)__float_as_uint(b) << 32) | __float_as_uint(a);
    put64(p, (v & ~kTagMask) | tagm);
}
__device__ __forceinline__ bool okff(unsigned long long v, unsigned long long tagm) { return (v & kTagMask) == tagm; }
__device__ __forceinline__ bool ok8(const ulonglong2& a, const ulonglong2& b, const ulonglong2& c, const ulonglong2& d, unsigned long long tagm) {
    return ((((a.x ^ tagm) | (a.y ^ tagm) | (b.x ^ tagm) | (b.y ^ tagm)) | ((c.x ^ tagm) | (c.y ^ tagm) | (d.x ^ tagm) | (d.y ^ tagm))) & kTagMask) == 0;
}
__device__ __forceinline__ ulonglong2 get2p(const unsigned long long* p, int live) {
    ulonglong2 v = make_ulonglong2(0ULL, 0ULL);
    asm volatile("{\n.reg .pred p;\nsetp.ne.u32 p, %3, 0;\n@p ld.relaxed.gpu.global.v2.u64 {%0,%1}, [%2];\n}"
                 : "+l"(v.x), "+l"(v.y) : "l"(p), "r"(live) : "memory");
    return v;
}
__device__ __forceinline__ float flo(unsigned long long v) { return __uint_as_float((uint32_t)v & ~0xFu); }
__device__ __forceinline__ float fhi(unsigned long long v) { return __uint_as_float((uint32_t)(v >> 32) & ~0xFu); }
__device__ __forceinline__ unsigned long long get1(const unsigned long long* p) {
    unsigned long long v;
    asm volatile("ld.relaxed.gpu.global.u64 %0, [%1];" : "=l"(v) : "l"(p) : "memory");
    return v;
}
__device__ __forceinline__ ulonglong2 get2(const unsigned long long* p) {
    ulonglong2 v;
    asm volatile("ld.relaxed.gpu.global.v2.u64 {%0,%1}, [%2];" : "=l"(v.x), "=l"(v.y) : "l"(p) : "memory");
    return v;
}
__device__ __forceinline__ uint32_t hi32(unsigned long long v) { return (uint32_t)(v >> 32); }
__device__ __forceinline__ uint32_t pack_bf16(float lo, float hi) {
    __nv_bfloat162 h = __floats2bfloat162_rn(lo, hi);
    return *reinterpret_cast<uint32_t*>(&h);
}
constexpr int SPIN_LIMIT = 1 << 21;
__device__ __forceinline__ int ktile_of(int i, int c) {
    const int idx = i * 64 + c, o = (idx * 4682) >> 16;
    return i < NSWEEP ? o * 16 + (idx - o * NSWEEP) : c * 16 + i;
}

__global__ void __launch_bounds__(NTHREADS, 1) fused_decode_kernel(const __grid_constant__ Params prm) {
    extern __shared__ __align__(128) unsigned char smem[];
    const uint32_t sb = ((uint32_t)__cvta_generic_to_shared(smem) + 1023u) & ~1023u;
    const int tid = threadIdx.x, warp = tid >> 5, lane = tid & 31;
    const int bid = blockIdx.x;
    const int br = bid >> 6, hkv = (bid >> 3) & 7, jo = bid & 7, bb = jo >> 2, sp = jo & 3;
    const int octet = bid >> 3;
    const uint32_t bar_full = sb + OFF_BAR, bar_empty = bar_full + RING * 8, bar_w = bar_empty + RING * 8, bar_wo = bar_w + 16, bar_go = bar_wo + 16;

    uint64_t pol;
    asm volatile("createpolicy.fractional.L2::evict_first.b64 %0, 1.0;" : "=l"(pol));

    const unsigned long long t0 = gtime();
    if (tid == NCONS) {
        mbar_init(bar_w, 1); mbar_init(bar_w + 8, 1);
        asm volatile("fence.proxy.async.shared::cta;" ::: "memory");
        const int col = hkv * 512 + jo * 64;
        mbar_expect_tx(bar_w, W_HALF + 4 * kD);
        tma2(sb + OFF_W, &prm.map[br][2], col, 0, bar_w, pol);
        bulk_load(sb + OFF_X, prm.x[br], 2 * kD, bar_w, pol);
        bulk_load(sb + OFF_X + XP * 2, prm.x[br] + kD, 2 * kD, bar_w, pol);
        mbar_expect_tx(bar_w + 8, W_HALF);
        tma2(sb + OFF_W + W_HALF, &prm.map[br][2], col, 224, bar_w + 8, pol);
#pragma unroll
        for (int s = 0; s < RING; s++) { mbar_init(bar_full + s * 8, 1); mbar_init(bar_empty + s * 8, 8); }
        mbar_init(bar_wo, 1); mbar_init(bar_wo + 8, 1); mbar_init(bar_go, 1);
        asm volatile("fence.mbarrier_init.release.cluster;" ::: "memory");
        asm volatile("fence.proxy.async.shared::cta;" ::: "memory");
    }

    if (warp == 8) {
        __syncthreads();
        if (lane == 0) {
            const int row0 = (bb * 8 + hkv) * 4096 + sp * 1024;
            const unsigned long long base = t0 + prm.off + ((bid * prm.stag) >> 7);
            uint32_t tsum = 0;
#pragma unroll 1
            for (int i = 0; i < 2 * NT + 2; i++) {
                const int slot = i % RING;
                const int eoff = i == 2 * NT + 1 ? prm.e1 : 0;
                if (i >= DEPTH) {
                    const int w = i - DEPTH;
                    mbar_wait(bar_full + (w % RING) * 8, (w / RING) & 1);
                    tsum += (uint32_t)(gtime() - base);
                    if ((w & 3) == 3) {
                        if ((bid & 3) == 0 && w >= 7 && w < 7 + 4 * NCHK) {
                            const unsigned long long v = ((unsigned long long)lds32(sb + OFF_TAG) << 32) | (tsum >> 2);
                            unsigned long long* p = &g_ctl[(((w - 7) >> 2) * 32 + (bid >> 2)) * 4];
                            asm volatile("st.relaxed.gpu.global.v2.u64 [%0], {%1, %1};" ::"l"(p), "l"(v) : "memory");
                            asm volatile("st.relaxed.gpu.global.v2.u64 [%0], {%1, %1};" ::"l"(p + 2), "l"(v) : "memory");
                        }
                        tsum = 0;
                    }
                }
                if (i < 2 * NT && i >= RING) mbar_wait(bar_empty + slot * 8, ((i / RING) - 1) & 1);
                for (int it = 0; it < (1 << 16) && (int)((uint32_t)(gtime() - base) - lds32(sb + OFF_DUE + i * 4)) < eoff; ++it) { }
                if (i < 2 * NT) {
                    mbar_expect_tx(bar_full + slot * 8, TILE_BYTES);
                    const int ot = ktile_of(i, bid & 63);
                    const int row = i < NT ? ((ot & 64) << 9) + ((ot >> 7) << 12) + (ot & 63) * 64 : row0 + (i - NT) * 64;
                    tma3(sb + OFF_RING + slot * TILE_BYTES, &prm.map[br][i >= NT], row, bar_full + slot * 8, pol);
                } else {
                    const int h = i - 2 * NT;
                    mbar_expect_tx(bar_wo + h * 8, W_HALF);
                    tma3(sb + OFF_W + h * W_HALF, &prm.map[br][3], hkv * 512 + jo * 64 + h * 32, bar_wo + h * 8, pol);
                }
            }
        }
        __syncwarp();
        {
            uint32_t tg;
            asm volatile("ld.shared.u32 %0, [%1];" : "=r"(tg) : "r"(sb + OFF_TAG) : "memory");
            const unsigned long long tagm = ((unsigned long long)(tg >> 4) << 32) | (tg & 15);
            const unsigned long long* p = &g_x1[((octet * 8 + jo) * 2 + (lane >> 4)) * 128 + (lane & 15) * 2];
            ulonglong2 v0, v1, v2, v3;
            int it = 0;
            do {
                v0 = get2(p); v1 = get2(p + 32); v2 = get2(p + 64); v3 = get2(p + 96);
                if (++it > SPIN_LIMIT) __trap();
            } while (!__all_sync(0xffffffffu, ok8(v0, v1, v2, v3, tagm)));
            const uint32_t oa = sb + OFF_O + (lane >> 4) * OP * 2 + (((lane & 15) >> 2) * 16 + (lane & 3) * 2) * 2;
            sts32(oa, pack_bf16((flo(v0.x) + flo(v1.x)) + (flo(v2.x) + flo(v3.x)), (flo(v0.y) + flo(v1.y)) + (flo(v2.y) + flo(v3.y))));
            sts32(oa + 16, pack_bf16((fhi(v0.x) + fhi(v1.x)) + (fhi(v2.x) + fhi(v3.x)), (fhi(v0.y) + fhi(v1.y)) + (fhi(v2.y) + fhi(v3.y))));
            asm volatile("bar.arrive 2, 288;" ::: "memory");
        }
        return;
    }

    if (warp == 9) {
        sts32(sb + OFF_DUE + lane * 4, lane * prm.pace);
        if (lane < 4) sts32(sb + OFF_DUE + 128 + lane * 4, (32 + lane) * prm.pace);
        __syncthreads();
        asm volatile("bar.sync 3, 64;" ::: "memory");
        if (prm.pace == 0) return;
        const uint32_t tag = lds32(sb + OFF_TAG);
        const unsigned long long base = t0 + prm.off + ((bid * prm.stag) >> 7);
        float cap = (float)prm.pace, tprev = 0.f, nest = 1.f;
#pragma unroll 1
        for (int k = 0; k < NCHK; k++) {
            const int c = 7 + 4 * k, a = c + LAG;
            for (int it = 0; it < (1 << 12) && (int)((uint32_t)(gtime() - base) - lds32(sb + OFF_DUE + (c + 3) * 4)) < 0; ++it) __nanosleep(100);
            unsigned long long v;
            int it = 0;
            do { v = get1(&g_ctl[(k * 32 + lane) * 4]); if (++it > SPIN_LIMIT) __trap(); } while (!__all_sync(0xffffffffu, hi32(v) == tag));
            const float T = (float)__reduce_add_sync(0xffffffffu, (uint32_t)v) * (1.f / 32.f);
            bool jump = false;
            if (k > 0) {
                const float est = (T - tprev) * 0.25f;
                jump = est > cap * 1.047f;
                if (!jump) { nest = fminf(nest + 1.f, 3.f); cap += (est - cap) / nest; }
            }
            tprev = T;
            const float da = (float)lds32(sb + OFF_DUE + a * 4);
            const float err = T + (LAG + 1.5f) * cap - da - (float)prm.lstar;
            jump = jump || err > 0.7f * cap;
            const float pn = jump ? cap : fminf(fmaxf(cap + err * (1.f / HOR), (float)prm.pmin), (float)prm.pmax);
            const float d0 = da + (jump ? fmaxf(err, 0.f) : 0.f);
            __syncwarp();
            if (a + lane < 36) sts32(sb + OFF_DUE + (a + lane) * 4, (uint32_t)(d0 + (float)lane * pn));
            __syncwarp();
        }
        return;
    }

    if (warp > 9) {
        const int ht = tid - (NCONS + 64);
        uint32_t tag;
        __syncthreads();
        asm volatile("ld.relaxed.gpu.global.u32 %0, [%1];" : "=r"(tag) : "l"(&g_epoch[bid]) : "memory");
        tag = tag >= 255 ? 1 : tag + 1;
        const unsigned long long tagm = ((unsigned long long)(tag >> 4) << 32) | (tag & 15);
        int it = 0;
        {
            const unsigned long long* p = &g_x0[br * 4096 + ht * 2];
            ulonglong2 v[8];
            const uint32_t qa = sb + OFF_QA + ((ht >> 7) * 2 + ((ht >> 6) & 1)) * (QP * 2) + (((ht & 63) >> 2) * 16 + (ht & 3) * 2) * 2;
            mbar_wait(bar_w + 8, 0);
            { const unsigned long long tw = gtime(); for (int w = 0; w < 256 && gtime() - tw < 300u; ++w) { } }
#pragma unroll
            for (int st = 0; st < 2; st++) {
                const int k0 = st ? 2 : 0, k1 = st ? 8 : 2;
#pragma unroll
                for (int k = k0; k < k1; k++) v[k] = get2(p + k * 512);
                for (;;) {
                    bool all = true;
#pragma unroll
                    for (int k = k0; k < k1; k++)
                        if (!__all_sync(0xffffffffu, hi32(v[k].x) == tag && hi32(v[k].y) == tag)) { v[k] = get2(p + k * 512); all = false; }
                    if (all) break;
                    if (++it > SPIN_LIMIT) __trap();
                }
                if (st == 0) asm volatile("bar.sync 4, 512;" ::: "memory");
#pragma unroll
                for (int k = k0; k < k1; k++) {
                    sts32(qa + k * (8 * QP), __byte_perm((uint32_t)v[k].x, (uint32_t)v[k].y, 0x5410));
                    sts32(qa + k * (8 * QP) + 16, __byte_perm((uint32_t)v[k].x, (uint32_t)v[k].y, 0x7632));
                }
                if (st == 0) asm volatile("bar.arrive 5, 512;" ::: "memory");
                else asm volatile("bar.arrive 6, 512;" ::: "memory");
            }
        }
        {
            const unsigned long long* p = &g_xs[bid * 896 + ht * 2];
            const bool two = ht < 192;
            ulonglong2 v0, v1;
            mbar_wait(bar_go, 0);
            do {
                v0 = get2(p); v1 = get2(two ? p + 512 : p);
                if (++it > SPIN_LIMIT) __trap();
            } while (!__all_sync(0xffffffffu, okff(v0.x, tagm) && okff(v0.y, tagm) && okff(v1.x, tagm) && okff(v1.y, tagm)));
            const uint32_t sa = sb + OFF_S + ht * 8;
            asm volatile("st.shared.v2.f32 [%0], {%1, %2};" ::"r"(sa), "f"(flo(v0.x)), "f"(flo(v0.y)) : "memory");
            asm volatile("st.shared.v2.f32 [%0], {%1, %2};" ::"r"(sa + HS * 4), "f"(fhi(v0.x)), "f"(fhi(v0.y)) : "memory");
            if (two) {
                asm volatile("st.shared.v2.f32 [%0], {%1, %2};" ::"r"(sa + 2048), "f"(flo(v1.x)), "f"(flo(v1.y)) : "memory");
                asm volatile("st.shared.v2.f32 [%0], {%1, %2};" ::"r"(sa + 2048 + HS * 4), "f"(fhi(v1.x)), "f"(fhi(v1.y)) : "memory");
            }
            asm volatile("bar.arrive 7, 512;" ::: "memory");
        }
        return;
    }

    __syncthreads();
    const int g = lane >> 2, t = lane & 3, mi = lane >> 3, r8 = lane & 7;
    const int grp = bid >> 2;
    unsigned long long* const px0 = &g_x0[octet * 512 + (t & 1) * 256 + jo * 32 + (warp & 3) * 8 + g];
    unsigned long long* const pxml = &g_xml[grp * 16 + sp * 4 + (lane & 3)];
    unsigned long long* const px1 = &g_x1[(((octet * 8 + (t & 1) * 4 + (warp >> 1)) * 2 + bb) * 4 + sp) * 32 + ((warp & 1) * 2 + (t >> 1)) * 8 + g];
    unsigned long long* const px2 = &g_x2[((size_t)(br * 56 + 2 * warp + (t & 1) + 16 * (t >> 1)) * 64 + (bid & 63)) * 8 + g];
    uint32_t tag;
    asm volatile("ld.relaxed.gpu.global.u32 %0, [%1];" : "=r"(tag) : "l"(&g_epoch[bid]) : "memory");
    if (warp < 4 && t < 2) put64(px0, 0);
    if (tid < 4) put64(pxml, 0);
    tag = tag >= 255 ? 1 : tag + 1;
    const unsigned long long tagm = ((unsigned long long)(tag >> 4) << 32) | (tag & 15);

    if (warp < 4) {
        float c0[4] = {0.f, 0.f, 0.f, 0.f}, c1[4] = {0.f, 0.f, 0.f, 0.f};
        const uint32_t wa = sb + OFF_W + (8 * (mi >> 1) + r8) * 128 + ((2 * warp + (mi & 1)) ^ r8) * 16;
        const uint32_t xa = sb + OFF_X + (g & 1) * XP * 2 + t * 4;
#pragma unroll
        for (int h = 0; h < 2; h++) {
            mbar_wait(bar_w + h * 8, 0);
#pragma unroll
            for (int ks = h * 14; ks < h * 14 + 14; ks += 2) {
                uint32_t a0[4], a1[4];
                ldsm4t(a0, wa + ks * 2048);
                ldsm4t(a1, wa + (ks + 1) * 2048);
                const uint32_t b00 = lds32(xa + ks * 32), b01 = lds32(xa + ks * 32 + 16);
                const uint32_t b10 = lds32(xa + ks * 32 + 32), b11 = lds32(xa + ks * 32 + 48);
                mma16816(c0, a0, b00, b01);
                mma16816(c1, a1, b10, b11);
            }
        }
        const uint32_t pk = (t & 1) ? pack_bf16(c0[1] + c1[1], c0[3] + c1[3]) : pack_bf16(c0[0] + c1[0], c0[2] + c1[2]);
        if (t < 2) put(px0, pk, tag);
    }
    asm volatile("bar.arrive 4, 512;" ::: "memory");
    asm volatile("bar.sync 5, 512;" ::: "memory");
    if (tid == 0) { g_epoch[bid] = tag; sts32(sb + OFF_TAG, tag); }
    if (warp == 0) { __syncwarp(); asm volatile("bar.arrive 3, 64;" ::: "memory"); }

    {
        const int u = warp & 3, par = warp >> 2;
        const uint32_t qa = sb + OFF_QA + (g & 1) * QP * 2 + t * 4;
        const uint32_t ka = sb + OFF_RING + (16 * u + 8 * (mi & 1) + r8) * 128 + ((mi >> 1) ^ r8) * 16;
        const int pos = (g >> 1) * 16 + u * 4 + (t & 1) * 2 + (g & 1);
#pragma unroll 1
        for (int i = 0; i < NT; i++) {
            const int slot = i % RING;
            if (i == 3) asm volatile("bar.sync 6, 512;" ::: "memory");
            if ((i & 1) == par) {
                const int ot = ktile_of(i, bid & 63);
                const uint32_t qg = qa + (ot >> 6) * (4 * QP);
                uint32_t qb[32];
#pragma unroll
                for (int kk = 0; kk < 16; kk++) { qb[2 * kk] = lds32(qg + kk * 32); qb[2 * kk + 1] = lds32(qg + kk * 32 + 16); }
                mbar_wait(bar_full + slot * 8, (i / RING) & 1);
                float c0[4] = {0.f, 0.f, 0.f, 0.f}, c1[4] = {0.f, 0.f, 0.f, 0.f};
#pragma unroll
                for (int hq = 0; hq < 2; hq++) {
                    uint32_t a[8][4];
#pragma unroll
                    for (int kk = 0; kk < 8; kk++) ldsm4(a[kk], ((ka ^ ((kk & 3) * 32)) + (hq * 2 + (kk >> 2)) * 8192) + slot * TILE_BYTES);
#pragma unroll
                    for (int kk = 0; kk < 8; kk += 2) {
                        mma16816(c0, a[kk], qb[hq * 16 + 2 * kk], qb[hq * 16 + 2 * kk + 1]);
                        mma16816(c1, a[kk + 1], qb[hq * 16 + 2 * kk + 2], qb[hq * 16 + 2 * kk + 3]);
                    }
                }
                const float s0 = (t & 1) ? c0[2] + c1[2] : c0[0] + c1[0], s1 = (t & 1) ? c0[3] + c1[3] : c0[1] + c1[1];
                if (i < NSWEEP) { if (t < 2) putff(&g_xs[(br * 64 + (ot >> 4)) * 896 + (ot & 15) * 64 + pos], s0, s1, tagm); }
                else sts32(sb + OFF_S + ((t >> 1) * HS + i * 64 + pos) * 4, __float_as_uint((t & 2) ? s1 : s0));
                if (i == NSWEEP && tid == 0) mbar_arrive(bar_go);
            } else {
                mbar_wait(bar_full + slot * 8, (i / RING) & 1);
            }
            __syncwarp();
            if (lane == 0) mbar_arrive(bar_empty + slot * 8);
        }
    }
    asm volatile("bar.sync 7, 512;" ::: "memory");

    constexpr float kScale = 0.0625f * 1.4426950408889634f;
    {
        const int h = warp >> 2;
        const uint32_t a0 = sb + OFF_S + (h * HS + (tid & 127) * 8) * 4;
        const uint4 x0 = lds128(a0), x1 = lds128(a0 + 16);
        float s[8] = {__uint_as_float(x0.x), __uint_as_float(x0.y), __uint_as_float(x0.z), __uint_as_float(x0.w),
                      __uint_as_float(x1.x), __uint_as_float(x1.y), __uint_as_float(x1.z), __uint_as_float(x1.w)};
        float m = fmaxf(fmaxf(fmaxf(s[0], s[1]), fmaxf(s[2], s[3])), fmaxf(fmaxf(s[4], s[5]), fmaxf(s[6], s[7])));
#pragma unroll
        for (int o = 16; o > 0; o >>= 1) m = fmaxf(m, __shfl_xor_sync(0xffffffffu, m, o));
        if (lane == 0) sts32(sb + OFF_WM + warp * 4, __float_as_uint(m));
        cons_sync();
        const uint4 wm = lds128(sb + OFF_WM + h * 16);
        m = fmaxf(fmaxf(__uint_as_float(wm.x), __uint_as_float(wm.y)), fmaxf(__uint_as_float(wm.z), __uint_as_float(wm.w)));
        float l = 0.f;
#pragma unroll
        for (int e = 0; e < 8; e++) { s[e] = exp2f((s[e] - m) * kScale); l += s[e]; }
        sts128(sb + OFF_P + h * PP * 2 + (tid & 127) * 16,
               make_uint4(pack_bf16(s[0], s[1]), pack_bf16(s[2], s[3]), pack_bf16(s[4], s[5]), pack_bf16(s[6], s[7])));
#pragma unroll
        for (int o = 16; o > 0; o >>= 1) l += __shfl_xor_sync(0xffffffffu, l, o);
        if (lane == 0) sts32(sb + OFF_WM + 32 + warp * 4, __float_as_uint(l));
        cons_sync();
        if (tid < 4) {
            const uint4 wm2 = lds128(sb + OFF_WM + (tid & 1) * 16), wl = lds128(sb + OFF_WM + 32 + (tid & 1) * 16);
            const float mt = fmaxf(fmaxf(__uint_as_float(wm2.x), __uint_as_float(wm2.y)), fmaxf(__uint_as_float(wm2.z), __uint_as_float(wm2.w)));
            const float lt = (__uint_as_float(wl.x) + __uint_as_float(wl.y)) + (__uint_as_float(wl.z) + __uint_as_float(wl.w));
            put(pxml, __float_as_uint((tid & 2) ? lt : mt), tag);
        }
    }

    float acc0[4] = {0.f, 0.f, 0.f, 0.f}, acc1[4] = {0.f, 0.f, 0.f, 0.f};
    float wgt = 0.f;
    const uint32_t va = sb + OFF_RING + (warp >> 1) * 8192 + (8 * (mi >> 1) + r8) * 128 + (((warp & 1) * 4 + (mi & 1)) ^ r8) * 16;
    const uint32_t pa = sb + OFF_P + (g & 1) * PP * 2 + t * 32;
    const uint32_t wa = sb + OFF_W + (warp >> 2) * 4096 + (8 * (mi >> 1) + r8) * 128 + ((((2 * warp) & 7) + (mi & 1)) ^ r8) * 16;
    const uint32_t oa = sb + OFF_O + (g & 1) * OP * 2 + t * 4;
    const int rr = bid & 63;
    __nv_bfloat16* outp = prm.out + ((tid >> 3) & 1) * (2 * kD) + br * kD + rr * 8 + (tid & 7);
    asm volatile("" : "+l"(outp));
    const unsigned long long* const pr2 = &g_x2[(size_t)(br * 56 + rr) * 512 + tid * 2];
#pragma unroll 1
    for (int pass = 0; pass < 2; pass++) {
        int live;
        asm volatile("mov.u32 %0, %1;" : "=r"(live) : "r"(pass));
        const unsigned long long tg = live ? tagm : 0ULL;
#pragma unroll 1
        for (int i = 0; i < live * NT; i++) {
            const int n = NT + i, slot = n % RING;
            if (i == NT - 3) {
                const unsigned long long* p = &g_xml[grp * 16 + (lane & 15)];
                unsigned long long v;
                int it = 0;
                do { v = get1(p); if (++it > SPIN_LIMIT) __trap(); } while (!__all_sync(0xffffffffu, hi32(v) == tag));
                const float f = __uint_as_float((uint32_t)v);
                float ms[4], ls[4];
#pragma unroll
                for (int s = 0; s < 4; s++) {
                    ms[s] = __shfl_sync(0xffffffffu, f, s * 4 + (t & 1));
                    ls[s] = __shfl_sync(0xffffffffu, f, s * 4 + 2 + (t & 1));
                }
                const float mloc = __shfl_sync(0xffffffffu, f, sp * 4 + (t & 1));
                const float M = fmaxf(fmaxf(ms[0], ms[1]), fmaxf(ms[2], ms[3]));
                float L = 0.f;
#pragma unroll
                for (int s = 0; s < 4; s++) L += ls[s] * exp2f((ms[s] - M) * kScale);
                wgt = exp2f((mloc - M) * kScale) / L;
            }
            const uint4 p0 = lds128(pa + i * 128), p1 = lds128(pa + i * 128 + 16);
            mbar_wait(bar_full + slot * 8, (n / RING) & 1);
            uint32_t a[8][4];
#pragma unroll
            for (int j = 0; j < 4; j++) {
                ldsm4t(a[2 * j], va + slot * TILE_BYTES + j * 2048);
                ldsm4t(a[2 * j + 1], (va ^ 32) + slot * TILE_BYTES + j * 2048);
            }
            mma16816(acc0, a[0], p0.x, p0.y); mma16816(acc1, a[1], p0.x, p0.y);
            mma16816(acc0, a[2], p0.z, p0.w); mma16816(acc1, a[3], p0.z, p0.w);
            mma16816(acc0, a[4], p1.x, p1.y); mma16816(acc1, a[5], p1.x, p1.y);
            mma16816(acc0, a[6], p1.z, p1.w); mma16816(acc1, a[7], p1.z, p1.w);
            __syncwarp();
            if (lane == 0) mbar_arrive(bar_empty + slot * 8);
        }
        {
            const float a0 = (t & 2) ? acc1[0] : acc0[0], a1 = (t & 2) ? acc1[1] : acc0[1];
            const float a2 = (t & 2) ? acc1[2] : acc0[2], a3 = (t & 2) ? acc1[3] : acc0[3];
            putff(px1, ((t & 1) ? a1 : a0) * wgt, ((t & 1) ? a3 : a2) * wgt, tg);
        }
        {
            uint32_t a[4][2][4];
            float c[4][4];
            uint32_t ob[8];
#pragma unroll
            for (int m = 0; m < 4; m++) { c[m][0] = c[m][1] = c[m][2] = c[m][3] = 0.f; }
            if (live) mbar_wait(bar_wo, 0);
#pragma unroll
            for (int m = 0; m < 4; m++)
                if (m < 3 || warp < 4) { ldsm4t(a[m][0], wa + m * 8192); ldsm4t(a[m][1], wa + m * 8192 + 2048); }
            if (live) asm volatile("bar.sync 2, 288;" ::: "memory");
#pragma unroll
            for (int ks = 0; ks < 4; ks++) { ob[2 * ks] = lds32(oa + ks * 32); ob[2 * ks + 1] = lds32(oa + ks * 32 + 16); }
#pragma unroll
            for (int ks = 0; ks < 2; ks++)
#pragma unroll
                for (int m = 0; m < 4; m++)
                    if (m < 3 || warp < 4) mma16816(c[m], a[m][ks], ob[2 * ks], ob[2 * ks + 1]);
            if (live) mbar_wait(bar_wo + 8, 0);
#pragma unroll
            for (int m = 0; m < 4; m++)
                if (m < 3 || warp < 4) { ldsm4t(a[m][0], wa + W_HALF + m * 8192); ldsm4t(a[m][1], wa + W_HALF + m * 8192 + 2048); }
#pragma unroll
            for (int ks = 0; ks < 2; ks++)
#pragma unroll
                for (int m = 0; m < 4; m++)
                    if (m < 3 || warp < 4) mma16816(c[m], a[m][ks], ob[4 + 2 * ks], ob[5 + 2 * ks]);
            {
                const float a0 = (t & 2) ? c[1][0] : c[0][0], a1 = (t & 2) ? c[1][1] : c[0][1];
                const float a2 = (t & 2) ? c[1][2] : c[0][2], a3 = (t & 2) ? c[1][3] : c[0][3];
                putff(px2, (t & 1) ? a2 : a0, (t & 1) ? a3 : a1, tg);
            }
            if (warp < 4 || t < 2) {
                const float a0 = (t & 2) ? c[3][0] : c[2][0], a1 = (t & 2) ? c[3][1] : c[2][1];
                const float a2 = (t & 2) ? c[3][2] : c[2][2], a3 = (t & 2) ? c[3][3] : c[2][3];
                putff(px2 + 32 * 64 * 8, (t & 1) ? a2 : a0, (t & 1) ? a3 : a1, tg);
            }
        }
        if (rr < 56) {
            ulonglong2 v;
            int it = 0;
            do {
                v = get2p(pr2, live);
                if (++it > SPIN_LIMIT) __trap();
            } while (!__all_sync(0xffffffffu, okff(v.x, tg) && okff(v.y, tg)));
            float s0 = flo(v.x), s1 = fhi(v.x), s2 = flo(v.y), s3 = fhi(v.y);
#pragma unroll
            for (int o = 4; o < 32; o <<= 1) {
                s0 += __shfl_xor_sync(0xffffffffu, s0, o); s1 += __shfl_xor_sync(0xffffffffu, s1, o);
                s2 += __shfl_xor_sync(0xffffffffu, s2, o); s3 += __shfl_xor_sync(0xffffffffu, s3, o);
            }
            if (lane < 16) {
                const float lo = (lane & 8) ? s1 : s0, hi = (lane & 8) ? s3 : s2;
                sts32(sb + OFF_RED + (warp * 16 + (lane & 8) + (lane & 3) * 2 + ((lane >> 2) & 1)) * 4, __float_as_uint((lane & 4) ? hi : lo));
            }
            cons_sync();
            if (tid < 16) {
                float f[8];
#pragma unroll
                for (int w = 0; w < 8; w++) f[w] = __uint_as_float(lds32(sb + OFF_RED + (w * 16 + tid) * 4));
                const float o = ((f[0] + f[1]) + (f[2] + f[3])) + ((f[4] + f[5]) + (f[6] + f[7]));
                if (live) asm volatile("st.global.u16 [%0], %1;" ::"l"(outp), "h"(__bfloat16_as_ushort(__float2bfloat16_rn(o))) : "memory");
            }
        }
    }
}

}

typedef CUresult (*EncodeTiledFn)(CUtensorMap*, CUtensorMapDataType, cuuint32_t, void*, const cuuint64_t*, const cuuint64_t*,
                                  const cuuint32_t*, const cuuint32_t*, CUtensorMapInterleave, CUtensorMapSwizzle,
                                  CUtensorMapL2promotion, CUtensorMapFloatOOBfill);

extern "C" void kernel_launch(void* const* d_in, const int* in_sizes, int n_in, void* d_out, int out_size) {
    (void)in_sizes; (void)n_in; (void)out_size;
    static EncodeTiledFn enc = nullptr;
    static double unit_ns = 0.0;
    if (!enc) {
        int dev = 0, khz = 0, bits = 0;
        cudaGetDevice(&dev);
        if (cudaDeviceGetAttribute(&khz, cudaDevAttrMemoryClockRate, dev) == cudaSuccess &&
            cudaDeviceGetAttribute(&bits, cudaDevAttrGlobalMemoryBusWidth, dev) == cudaSuccess && khz > 0 && bits > 0)
            unit_ns = (double)NCTA * TILE_BYTES / (2.0 * khz * 1e-6 * bits / 8.0);
        (void)cudaGetLastError();
        cudaDriverEntryPointQueryResult qr;
        cudaGetDriverEntryPoint("cuTensorMapEncodeTiled", (void**)&enc, cudaEnableDefault, &qr);
        cudaFuncSetAttribute(fused_decode_kernel, cudaFuncAttributeMaxDynamicSharedMemorySize, SMEM_BYTES);
    }
    Params p;
    const cuuint32_t es[3] = {1, 1, 1};
    for (int b = 0; b < 2; b++) {
        p.x[b] = (const __nv_bfloat16*)d_in[b * 5 + 0];
        for (int kv = 0; kv < 2; kv++) {
            const cuuint64_t gd[3] = {64, 65536, 4}, gs[2] = {512, 128};
            const cuuint32_t bd[3] = {64, 64, 4};
            enc(&p.map[b][kv], CU_TENSOR_MAP_DATA_TYPE_BFLOAT16, 3, d_in[b * 5 + 1 + kv], gd, gs, bd, es, CU_TENSOR_MAP_INTERLEAVE_NONE,
                CU_TENSOR_MAP_SWIZZLE_128B, CU_TENSOR_MAP_L2_PROMOTION_L2_256B, CU_TENSOR_MAP_FLOAT_OOB_FILL_NONE);
        }
        {
            const cuuint64_t gd[2] = {4096, 448}, gs[1] = {8192};
            const cuuint32_t bd[2] = {64, 224};
            enc(&p.map[b][2], CU_TENSOR_MAP_DATA_TYPE_BFLOAT16, 2, d_in[b * 5 + 3], gd, gs, bd, es, CU_TENSOR_MAP_INTERLEAVE_NONE,
                CU_TENSOR_MAP_SWIZZLE_128B, CU_TENSOR_MAP_L2_PROMOTION_L2_256B, CU_TENSOR_MAP_FLOAT_OOB_FILL_NONE);
        }
        {
            const cuuint64_t gd[3] = {64, 4096, 7}, gs[2] = {896, 128};
            const cuuint32_t bd[3] = {64, 32, 7};
            enc(&p.map[b][3], CU_TENSOR_MAP_DATA_TYPE_BFLOAT16, 3, d_in[b * 5 + 4], gd, gs, bd, es, CU_TENSOR_MAP_INTERLEAVE_NONE,
                CU_TENSOR_MAP_SWIZZLE_128B, CU_TENSOR_MAP_L2_PROMOTION_L2_256B, CU_TENSOR_MAP_FLOAT_OOB_FILL_NONE);
        }
    }
    p.out = (__nv_bfloat16*)d_out;
    const double u = unit_ns;
    p.pace = (int)(u * 1.023); p.pmin = (int)(u * 1.009); p.pmax = (int)(u * 1.071);
    p.off = (int)(u * 1.28); p.stag = (int)(u * 1.0); p.lstar = (int)(u * 1.48); p.e1 = (int)(u * 0.14);
    fused_decode_kernel<<<NCTA, NTHREADS, SMEM_BYTES>>>(p);
}
```
